```python
import torch

def _softmax(x, axis=-1):
    return torch.softmax(x, dim=axis)
def _gelu(x):
    return torch.nn.functional.gelu(x, approximate="tanh")
def _silu(x):
    return torch.nn.functional.silu(x)
def _sigmoid(x):
    return torch.sigmoid(x)
def _layernorm(x, axis=-1, eps=1e-5):
    m = x.mean(dim=axis, keepdim=True)
    v = x.var(dim=axis, keepdim=True, unbiased=False)
    return (x - m) / torch.sqrt(v + eps)
def _scatter_add(tgt, idx, src, axis=0):
    return tgt.clone().index_add_(axis, idx, src)
def _segment_sum(src, seg, n):
    out = torch.zeros((n,) + src.shape[1:], dtype=src.dtype)
    return out.index_add_(0, seg, src)
def _pad(x, pw):
    flat = tuple(v for pair in reversed(pw) for v in pair)
    return torch.nn.functional.pad(x, flat)

kernel_name = 'sequential_preLN__grouped_kv_mqa__dense_activation_gelu__prompt'

def setup_inputs():

    _w = (lambda a: (lambda t: t.to(torch.bfloat16) if t.is_floating_point() else t)(torch.as_tensor(a)))
    def _A_setup():
        B, S, D, H = 1, 2048, 448, 16
        Dh = D // H
        return {
            "x": _w((lambda *s: torch.randn(*s, dtype=torch.bfloat16) * 0.05)(B, S, D)),
            "wq": _w((lambda *s: torch.randn(*s, dtype=torch.bfloat16) * 0.05)(D, H * Dh)),
            "wk": _w((lambda *s: torch.randn(*s, dtype=torch.bfloat16) * 0.05)(D, Dh)),
            "wv": _w((lambda *s: torch.randn(*s, dtype=torch.bfloat16) * 0.05)(D, Dh)),
            "wo": _w((lambda *s: torch.randn(*s, dtype=torch.bfloat16) * 0.05)(H * Dh, D)),
        }
    _A_in = _A_setup()

    def _B_setup():
        B, S, D, F = 1, 2048, 448, 1792
        return {
            "x": _w((lambda *s: torch.randn(*s, dtype=torch.bfloat16) * 0.05)(B, S, D)),
            "w1": _w((lambda *s: torch.randn(*s, dtype=torch.bfloat16) * 0.8)(D, F) * (D ** -0.5)),
            "b1": _w((lambda *s: torch.randn(*s, dtype=torch.bfloat16) * 12.8)(F) * 0.01),
            "w2": _w((lambda *s: torch.randn(*s, dtype=torch.bfloat16) * 0.4)(F, D) * (F ** -0.5)),
            "b2": _w((lambda *s: torch.randn(*s, dtype=torch.bfloat16) * 6.4)(D) * 0.01),
        }
    _B_in = _B_setup()

    return {
        "A_x": _A_in["x"],
        "A_wq": _A_in["wq"],
        "A_wk": _A_in["wk"],
        "A_wv": _A_in["wv"],
        "A_wo": _A_in["wo"],
        "B_x": _B_in["x"],
        "B_w1": _B_in["w1"],
        "B_b1": _B_in["b1"],
        "B_w2": _B_in["w2"],
        "B_b2": _B_in["b2"],
    }

def reference(A_x, A_wq, A_wk, A_wv, A_wo, B_x, B_w1, B_b1, B_w2, B_b2):
    def _A_ref(x, wq, wk, wv, wo):
        B, S, D = x.shape
        H = 16
        Dh = D // H
        q = (lambda x, *d: x.permute(*d))((x @ wq).reshape(B, S, H, Dh), 0, 2, 1, 3)
        k = x @ wk
        v = x @ wv
        scores = torch.einsum("bhqd,bkd->bhqk", q, k) * (Dh ** -0.5)
        p = _softmax(scores, axis=-1)
        o = torch.einsum("bhqk,bkd->bhqd", p, v)
        return (lambda x, *d: x.permute(*d))(o, 0, 2, 1, 3).reshape(B, S, H * Dh) @ wo

    def _B_ref(x, w1, b1, w2, b2):
        h = torch.einsum("bsd,df->bsf", x, w1) + b1
        h = _gelu(h)
        return torch.einsum("bsf,fd->bsd", h, w2) + b2

    x = A_x
    h = x + _A_ref(_layernorm(x, axis=-1), A_wq, A_wk, A_wv, A_wo)
    h2 = h + _B_ref(_layernorm(h, axis=-1), B_w1, B_b1, B_w2, B_b2)
    return h2
```

```cpp
#include <cuda_runtime.h>
#include <cuda_bf16.h>
#include <cuda.h>
#include <stdint.h>

namespace {

constexpr int SEQ = 2048, DM = 448, FF = 1792;
constexpr int NTHREADS = 512;
constexpr uint32_t SLOT = 28672;
constexpr uint32_t HSLOT = SLOT / 2;
constexpr uint32_t OFF_RING = 2 * SLOT + 20480;
constexpr uint32_t OFF_BAR = 8 * SLOT;
constexpr uint32_t OFF_B1 = OFF_BAR + 768;
constexpr uint32_t OFF_KMAX = OFF_B1 + 1792;
constexpr uint32_t SMEM_BYTES = OFF_KMAX + 64;
constexpr uint32_t POLY_MASK = 0xB5B7u;
constexpr float SHIFT_LIMIT = 48.f;
constexpr uint32_t SPIN_LIMIT = 1u << 24;

enum : uint32_t {
  B_WQ = 0, B_KVD = 7, B_QST = 8, B_KMAX = 9, B_KVF = 10, B_WO = 14, B_PRDY = 21, B_RCV1 = 22, B_QST2 = 23, B_R1 = 24, B_OUTW = 25,
  B_HN = 27, B_WF = 34, B_WE = 41, B_F1 = 48, B_PF1 = 49, B_W2E = 50, B_RCV2 = 57, B_W2F = 64, B_KVE = 71, B_X = 72
};

struct alignas(128) GroupSync { uint32_t hn_count, out_count; };
struct Sync { uint32_t kv_count, pad0; unsigned long long kmax; GroupSync grp[16]; };
__device__ __align__(128) Sync g_sync;
__device__ __align__(1024) uint8_t g_kv[SEQ * 128];
__device__ __align__(1024) uint8_t g_hn[SEQ * DM * 2];

__device__ __forceinline__ void wgmma_ss_n32_t10(float (&d)[16], uint64_t ad, uint64_t bd, int sc) {
  asm volatile("{.reg .pred p; setp.ne.b32 p, %18, 0;\n"
    "wgmma.mma_async.sync.aligned.m64n32k16.f32.bf16.bf16 {%0, %1, %2, %3, %4, %5, %6, %7, %8, %9, %10, %11, %12, %13, %14, %15}, %16, %17, p, 1, 1, 1, 0;}\n"
    : "+f"(d[0]), "+f"(d[1]), "+f"(d[2]), "+f"(d[3]), "+f"(d[4]), "+f"(d[5]), "+f"(d[6]), "+f"(d[7]), "+f"(d[8]), "+f"(d[9]), "+f"(d[10]), "+f"(d[11]), "+f"(d[12]), "+f"(d[13]), "+f"(d[14]), "+f"(d[15])
    : "l"(ad), "l"(bd), "r"(sc));
}
__device__ __forceinline__ void wgmma_rs_n128_t0(float (&d)[64], uint32_t a0, uint32_t a1, uint32_t a2, uint32_t a3, uint64_t bd, int sc) {
  asm volatile("{.reg .pred p; setp.ne.b32 p, %69, 0;\n"
    "wgmma.mma_async.sync.aligned.m64n128k16.f32.bf16.bf16 {%0, %1, %2, %3, %4, %5, %6, %7, %8, %9, %10, %11, %12, %13, %14, %15, %16, %17, %18, %19, %20, %21, %22, %23, %24, %25, %26, %27, %28, %29, %30, %31, %32, %33, %34, %35, %36, %37, %38, %39, %40, %41, %42, %43, %44, %45, %46, %47, %48, %49, %50, %51, %52, %53, %54, %55, %56, %57, %58, %59, %60, %61, %62, %63}, {%64, %65, %66, %67}, %68, p, 1, 1, 0;}\n"
    : "+f"(d[0]), "+f"(d[1]), "+f"(d[2]), "+f"(d[3]), "+f"(d[4]), "+f"(d[5]), "+f"(d[6]), "+f"(d[7]), "+f"(d[8]), "+f"(d[9]), "+f"(d[10]), "+f"(d[11]), "+f"(d[12]), "+f"(d[13]), "+f"(d[14]), "+f"(d[15]), "+f"(d[16]), "+f"(d[17]), "+f"(d[18]), "+f"(d[19]), "+f"(d[20]), "+f"(d[21]), "+f"(d[22]), "+f"(d[23]), "+f"(d[24]), "+f"(d[25]), "+f"(d[26]), "+f"(d[27]), "+f"(d[28]), "+f"(d[29]), "+f"(d[30]), "+f"(d[31]), "+f"(d[32]), "+f"(d[33]), "+f"(d[34]), "+f"(d[35]), "+f"(d[36]), "+f"(d[37]), "+f"(d[38]), "+f"(d[39]), "+f"(d[40]), "+f"(d[41]), "+f"(d[42]), "+f"(d[43]), "+f"(d[44]), "+f"(d[45]), "+f"(d[46]), "+f"(d[47]), "+f"(d[48]), "+f"(d[49]), "+f"(d[50]), "+f"(d[51]), "+f"(d[52]), "+f"(d[53]), "+f"(d[54]), "+f"(d[55]), "+f"(d[56]), "+f"(d[57]), "+f"(d[58]), "+f"(d[59]), "+f"(d[60]), "+f"(d[61]), "+f"(d[62]), "+f"(d[63])
    : "r"(a0), "r"(a1), "r"(a2), "r"(a3), "l"(bd), "r"(sc));
}
__device__ __forceinline__ void wgmma_rs_n32_t1(float (&d)[16], uint32_t a0, uint32_t a1, uint32_t a2, uint32_t a3, uint64_t bd, int sc) {
  asm volatile("{.reg .pred p; setp.ne.b32 p, %21, 0;\n"
    "wgmma.mma_async.sync.aligned.m64n32k16.f32.bf16.bf16 {%0, %1, %2, %3, %4, %5, %6, %7, %8, %9, %10, %11, %12, %13, %14, %15}, {%16, %17, %18, %19}, %20, p, 1, 1, 1;}\n"
    : "+f"(d[0]), "+f"(d[1]), "+f"(d[2]), "+f"(d[3]), "+f"(d[4]), "+f"(d[5]), "+f"(d[6]), "+f"(d[7]), "+f"(d[8]), "+f"(d[9]), "+f"(d[10]), "+f"(d[11]), "+f"(d[12]), "+f"(d[13]), "+f"(d[14]), "+f"(d[15])
    : "r"(a0), "r"(a1), "r"(a2), "r"(a3), "l"(bd), "r"(sc));
}
__device__ __forceinline__ void wgmma_rs_n64_t1(float (&d)[32], uint32_t a0, uint32_t a1, uint32_t a2, uint32_t a3, uint64_t bd, int sc) {
  asm volatile("{.reg .pred p; setp.ne.b32 p, %37, 0;\n"
    "wgmma.mma_async.sync.aligned.m64n64k16.f32.bf16.bf16 {%0, %1, %2, %3, %4, %5, %6, %7, %8, %9, %10, %11, %12, %13, %14, %15, %16, %17, %18, %19, %20, %21, %22, %23, %24, %25, %26, %27, %28, %29, %30, %31}, {%32, %33, %34, %35}, %36, p, 1, 1, 1;}\n"
    : "+f"(d[0]), "+f"(d[1]), "+f"(d[2]), "+f"(d[3]), "+f"(d[4]), "+f"(d[5]), "+f"(d[6]), "+f"(d[7]), "+f"(d[8]), "+f"(d[9]), "+f"(d[10]), "+f"(d[11]), "+f"(d[12]), "+f"(d[13]), "+f"(d[14]), "+f"(d[15]), "+f"(d[16]), "+f"(d[17]), "+f"(d[18]), "+f"(d[19]), "+f"(d[20]), "+f"(d[21]), "+f"(d[22]), "+f"(d[23]), "+f"(d[24]), "+f"(d[25]), "+f"(d[26]), "+f"(d[27]), "+f"(d[28]), "+f"(d[29]), "+f"(d[30]), "+f"(d[31])
    : "r"(a0), "r"(a1), "r"(a2), "r"(a3), "l"(bd), "r"(sc));
}
__device__ __forceinline__ void wgmma_ss_n128_t01(float (&d)[64], uint64_t ad, uint64_t bd, int sc) {
  asm volatile("{.reg .pred p; setp.ne.b32 p, %66, 0;\n"
    "wgmma.mma_async.sync.aligned.m64n128k16.f32.bf16.bf16 {%0, %1, %2, %3, %4, %5, %6, %7, %8, %9, %10, %11, %12, %13, %14, %15, %16, %17, %18, %19, %20, %21, %22, %23, %24, %25, %26, %27, %28, %29, %30, %31, %32, %33, %34, %35, %36, %37, %38, %39, %40, %41, %42, %43, %44, %45, %46, %47, %48, %49, %50, %51, %52, %53, %54, %55, %56, %57, %58, %59, %60, %61, %62, %63}, %64, %65, p, 1, 1, 0, 1;}\n"
    : "+f"(d[0]), "+f"(d[1]), "+f"(d[2]), "+f"(d[3]), "+f"(d[4]), "+f"(d[5]), "+f"(d[6]), "+f"(d[7]), "+f"(d[8]), "+f"(d[9]), "+f"(d[10]), "+f"(d[11]), "+f"(d[12]), "+f"(d[13]), "+f"(d[14]), "+f"(d[15]), "+f"(d[16]), "+f"(d[17]), "+f"(d[18]), "+f"(d[19]), "+f"(d[20]), "+f"(d[21]), "+f"(d[22]), "+f"(d[23]), "+f"(d[24]), "+f"(d[25]), "+f"(d[26]), "+f"(d[27]), "+f"(d[28]), "+f"(d[29]), "+f"(d[30]), "+f"(d[31]), "+f"(d[32]), "+f"(d[33]), "+f"(d[34]), "+f"(d[35]), "+f"(d[36]), "+f"(d[37]), "+f"(d[38]), "+f"(d[39]), "+f"(d[40]), "+f"(d[41]), "+f"(d[42]), "+f"(d[43]), "+f"(d[44]), "+f"(d[45]), "+f"(d[46]), "+f"(d[47]), "+f"(d[48]), "+f"(d[49]), "+f"(d[50]), "+f"(d[51]), "+f"(d[52]), "+f"(d[53]), "+f"(d[54]), "+f"(d[55]), "+f"(d[56]), "+f"(d[57]), "+f"(d[58]), "+f"(d[59]), "+f"(d[60]), "+f"(d[61]), "+f"(d[62]), "+f"(d[63])
    : "l"(ad), "l"(bd), "r"(sc));
}
__device__ __forceinline__ void wgmma_ss_n96_t01(float (&d)[48], uint64_t ad, uint64_t bd, int sc) {
  asm volatile("{.reg .pred p; setp.ne.b32 p, %50, 0;\n"
    "wgmma.mma_async.sync.aligned.m64n96k16.f32.bf16.bf16 {%0, %1, %2, %3, %4, %5, %6, %7, %8, %9, %10, %11, %12, %13, %14, %15, %16, %17, %18, %19, %20, %21, %22, %23, %24, %25, %26, %27, %28, %29, %30, %31, %32, %33, %34, %35, %36, %37, %38, %39, %40, %41, %42, %43, %44, %45, %46, %47}, %48, %49, p, 1, 1, 0, 1;}\n"
    : "+f"(d[0]), "+f"(d[1]), "+f"(d[2]), "+f"(d[3]), "+f"(d[4]), "+f"(d[5]), "+f"(d[6]), "+f"(d[7]), "+f"(d[8]), "+f"(d[9]), "+f"(d[10]), "+f"(d[11]), "+f"(d[12]), "+f"(d[13]), "+f"(d[14]), "+f"(d[15]), "+f"(d[16]), "+f"(d[17]), "+f"(d[18]), "+f"(d[19]), "+f"(d[20]), "+f"(d[21]), "+f"(d[22]), "+f"(d[23]), "+f"(d[24]), "+f"(d[25]), "+f"(d[26]), "+f"(d[27]), "+f"(d[28]), "+f"(d[29]), "+f"(d[30]), "+f"(d[31]), "+f"(d[32]), "+f"(d[33]), "+f"(d[34]), "+f"(d[35]), "+f"(d[36]), "+f"(d[37]), "+f"(d[38]), "+f"(d[39]), "+f"(d[40]), "+f"(d[41]), "+f"(d[42]), "+f"(d[43]), "+f"(d[44]), "+f"(d[45]), "+f"(d[46]), "+f"(d[47])
    : "l"(ad), "l"(bd), "r"(sc));
}

__device__ __forceinline__ void wg_fence() { asm volatile("wgmma.fence.sync.aligned;" ::: "memory"); }
__device__ __forceinline__ void wg_commit() { asm volatile("wgmma.commit_group.sync.aligned;" ::: "memory"); }
template <int N> __device__ __forceinline__ void wg_wait() { asm volatile("wgmma.wait_group.sync.aligned %0;" ::"n"(N) : "memory"); }
template <int N> __device__ __forceinline__ void pin(float (&a)[N]) {
#pragma unroll
  for (int i = 0; i < N; i++) asm volatile("" : "+f"(a[i])::"memory");
}
template <int N> __device__ __forceinline__ void pin(uint32_t (&a)[N]) {
#pragma unroll
  for (int i = 0; i < N; i++) asm volatile("" : "+r"(a[i])::"memory");
}
constexpr uint32_t HI128 = (1024u >> 4) | (1u << 30), HI64 = (512u >> 4) | (2u << 30), HI0 = 128u >> 4;
__device__ __forceinline__ uint32_t dlo(uint32_t addr, uint32_t lbo) { return ((addr & 0x3FFFF) >> 4) | ((lbo >> 4) << 16); }
template <uint32_t HI> __device__ __forceinline__ uint64_t desc(uint32_t lo) { uint64_t d; asm("mov.b64 %0, {%1, %2};" : "=l"(d) : "r"(lo), "n"(HI)); return d; }

__device__ __forceinline__ uint32_t uni(uint32_t v) { return __shfl_sync(0xffffffffu, v, 0); }

__device__ __forceinline__ uint32_t hold(uint32_t v, int lane) { return __shfl_sync(0xffffffffu, v, lane); }

__device__ __forceinline__ void mbar_init(uint32_t b, uint32_t n) { asm volatile("mbarrier.init.shared::cta.b64 [%0], %1;" ::"r"(b), "r"(n) : "memory"); }
__device__ __forceinline__ void mbar_expect(uint32_t b, uint32_t bytes) { asm volatile("mbarrier.arrive.expect_tx.shared::cta.b64 _, [%0], %1;" ::"r"(b), "r"(bytes) : "memory"); }
__device__ __forceinline__ void mbar_arrive(uint32_t b) { asm volatile("mbarrier.arrive.shared::cta.b64 _, [%0];" ::"r"(b) : "memory"); }
__device__ __forceinline__ void mbar_wait(uint32_t b, uint32_t ph = 0) {
  asm volatile("{.reg .pred p; .reg .u32 n; mov.u32 n, 0;\n"
               "W: mbarrier.try_wait.parity.shared::cta.b64 p, [%0], %1; @p bra D; add.u32 n, n, 1; setp.lt.u32 p, n, %2; @p bra W; trap;\n"
               "D: }" ::"r"(b), "r"(ph), "n"(SPIN_LIMIT) : "memory");
}
__device__ __forceinline__ void mbar_wait_hot(uint32_t b, uint32_t ph = 0) {
  asm volatile("{.reg .pred p; .reg .u32 n;\n"
               "mbarrier.try_wait.parity.shared::cta.b64 p, [%0], %1; @p bra D; mov.u32 n, 0;\n"
               "W: mbarrier.try_wait.parity.shared::cta.b64 p, [%0], %1; @p bra D; add.u32 n, n, 1; setp.lt.u32 p, n, %2; @p bra W; trap;\n"
               "D: }" ::"r"(b), "r"(ph), "n"(SPIN_LIMIT) : "memory");
}
__device__ __forceinline__ void warp_arrive(uint32_t b, int lane) { __syncwarp(); if (lane == 0) mbar_arrive(b); }
__device__ __forceinline__ void bar_sync(int id, int n) { asm volatile("bar.sync %0, %1;" ::"r"(id), "r"(n) : "memory"); }
__device__ __forceinline__ bool bar_all(int id, int n, bool v) {
  uint32_t r;
  asm volatile("{.reg .pred p, q; setp.ne.u32 p, %1, 0; bar.red.and.pred q, %2, %3, p; selp.u32 %0, 1, 0, q;}" : "=r"(r) : "r"((uint32_t)v), "r"(id), "r"(n) : "memory");
  return r;
}
__device__ __forceinline__ bool mbar_try(uint32_t b) {
  uint32_t ok;
  asm volatile("{.reg .pred p; mbarrier.test_wait.parity.shared::cta.b64 p, [%1], 0; selp.u32 %0, 1, 0, p;}" : "=r"(ok) : "r"(b) : "memory");
  return ok;
}
__device__ __forceinline__ void bar_arrive(int id, int n) { asm volatile("bar.arrive %0, %1;" ::"r"(id), "r"(n) : "memory"); }
__device__ __forceinline__ void bar_arrive_if(bool pred, int id, int n) {
  asm volatile("{.reg .pred p; setp.ne.u32 p, %2, 0; @p bar.arrive %0, %1;}" ::"r"(id), "r"(n), "r"((uint32_t)pred) : "memory");
}
__device__ __forceinline__ void lane0_arrive(uint32_t b, int lane) {
  asm volatile("{.reg .pred p; setp.eq.u32 p, %1, 0; @p mbarrier.arrive.shared::cta.b64 _, [%0];}" ::"r"(b), "r"(lane) : "memory");
}
__device__ __forceinline__ void wait_count(const uint32_t* p, uint32_t target) {
  asm volatile("{.reg .pred p; .reg .u32 n; .reg .s32 v; mov.u32 n, 0;\n"
               "W: ld.acquire.gpu.global.u32 v, [%0]; sub.s32 v, v, %1; setp.ge.s32 p, v, 0; @p bra D; add.u32 n, n, 1; setp.lt.u32 p, n, %2; @p bra W; trap;\n"
               "D: }" ::"l"(p), "r"(target), "n"(SPIN_LIMIT) : "memory");
}
__device__ __forceinline__ void fence_async() { asm volatile("fence.proxy.async;" ::: "memory"); }
__device__ __forceinline__ void fence_async_smem() { asm volatile("fence.proxy.async.shared::cta;" ::: "memory"); }
__device__ __forceinline__ uint32_t mapa(uint32_t a, uint32_t rank) { uint32_t r; asm("mapa.shared::cluster.u32 %0, %1, %2;" : "=r"(r) : "r"(a), "r"(rank)); return r; }

__device__ __forceinline__ void tma2d(uint32_t dst, const CUtensorMap* tm, int c0, int c1, uint32_t bar) {
  asm volatile("{.reg .pred p; elect.sync _|p, 0xffffffff;\n"
               "@p cp.async.bulk.tensor.2d.shared::cluster.global.mbarrier::complete_tx::bytes [%0], [%1, {%3, %4}], [%2];}"
               ::"r"(dst), "l"(tm), "r"(bar), "r"(c0), "r"(c1) : "memory");
}
__device__ __forceinline__ void bulk_g2s(uint32_t dst, const void* src, uint32_t bytes, uint32_t bar) {
  asm volatile("{.reg .pred p; elect.sync _|p, 0xffffffff; @p mbarrier.arrive.expect_tx.shared::cta.b64 _, [%3], %2;\n"
               "@p cp.async.bulk.shared::cluster.global.mbarrier::complete_tx::bytes [%0], [%1], %2, [%3];}"
               ::"r"(dst), "l"(src), "r"(bytes), "r"(bar) : "memory");
}
__device__ __forceinline__ void prefetch_l2(const void* src, uint32_t bytes) {
  asm volatile("{.reg .pred p; elect.sync _|p, 0xffffffff; @p cp.async.bulk.prefetch.L2.global [%0], %1;}" ::"l"(src), "r"(bytes) : "memory");
}
__device__ __forceinline__ void elect_expect(uint32_t b, uint32_t bytes) {
  asm volatile("{.reg .pred p; elect.sync _|p, 0xffffffff; @p mbarrier.arrive.expect_tx.shared::cta.b64 _, [%0], %1;}" ::"r"(b), "r"(bytes) : "memory");
}
__device__ __forceinline__ void elect_arrive(uint32_t b) {
  asm volatile("{.reg .pred p; elect.sync _|p, 0xffffffff; @p mbarrier.arrive.shared::cta.b64 _, [%0];}" ::"r"(b) : "memory");
}
__device__ __forceinline__ void elect_arrive_remote(uint32_t b) {
  asm volatile("{.reg .pred p; elect.sync _|p, 0xffffffff; @p mbarrier.arrive.shared::cluster.b64 _, [%0];}" ::"r"(b) : "memory");
}
__device__ __forceinline__ void elect_red(uint32_t* p) {
  asm volatile("{.reg .pred p; elect.sync _|p, 0xffffffff; @p red.relaxed.gpu.global.add.u32 [%0], 1;}" ::"l"(p) : "memory");
}
__device__ __forceinline__ void st_async4(uint32_t dst, uint32_t a, uint32_t b, uint32_t c, uint32_t d, uint32_t bar) {
  asm volatile("st.async.weak.shared::cluster.mbarrier::complete_tx::bytes.v4.b32 [%0], {%1, %2, %3, %4}, [%5];" ::"r"(dst), "r"(a), "r"(b), "r"(c), "r"(d), "r"(bar) : "memory");
}
__device__ __forceinline__ void stsm4(uint32_t a, uint32_t r0, uint32_t r1, uint32_t r2, uint32_t r3) {
  asm volatile("stmatrix.sync.aligned.m8n8.x4.shared.b16 [%0], {%1, %2, %3, %4};" ::"r"(a), "r"(r0), "r"(r1), "r"(r2), "r"(r3) : "memory");
}
__device__ __forceinline__ void stsm4t(uint32_t a, uint32_t r0, uint32_t r1, uint32_t r2, uint32_t r3) {
  asm volatile("stmatrix.sync.aligned.m8n8.x4.trans.shared.b16 [%0], {%1, %2, %3, %4};" ::"r"(a), "r"(r0), "r"(r1), "r"(r2), "r"(r3) : "memory");
}
__device__ __forceinline__ uint4 ldg128(const void* p, bool pred) {
  uint4 v = make_uint4(0, 0, 0, 0);
  asm volatile("{.reg .pred p; setp.ne.u32 p, %5, 0; @p ld.global.nc.v4.b32 {%0, %1, %2, %3}, [%4];}"
               : "+r"(v.x), "+r"(v.y), "+r"(v.z), "+r"(v.w) : "l"(p), "r"((uint32_t)pred));
  return v;
}
__device__ __forceinline__ uint32_t lds32(uint32_t a) { uint32_t v; asm volatile("ld.shared.b32 %0, [%1];" : "=r"(v) : "r"(a) : "memory"); return v; }
__device__ __forceinline__ uint4 lds128(uint32_t a) { uint4 v; asm volatile("ld.shared.v4.b32 {%0, %1, %2, %3}, [%4];" : "=r"(v.x), "=r"(v.y), "=r"(v.z), "=r"(v.w) : "r"(a) : "memory"); return v; }
__device__ __forceinline__ void sts32(uint32_t a, uint32_t v) { asm volatile("st.shared.b32 [%0], %1;" ::"r"(a), "r"(v) : "memory"); }
__device__ __forceinline__ void sts64(uint32_t a, uint32_t x, uint32_t y) { asm volatile("st.shared.v2.b32 [%0], {%1, %2};" ::"r"(a), "r"(x), "r"(y) : "memory"); }
__device__ __forceinline__ void sts128(uint32_t a, uint4 v) { asm volatile("st.shared.v4.b32 [%0], {%1, %2, %3, %4};" ::"r"(a), "r"(v.x), "r"(v.y), "r"(v.z), "r"(v.w) : "memory"); }

__device__ __forceinline__ uint32_t pack2(float lo, float hi) { uint32_t r; asm("cvt.rn.bf16x2.f32 %0, %1, %2;" : "=r"(r) : "f"(hi), "f"(lo)); return r; }
__device__ __forceinline__ float bf_lo(uint32_t v) { return __uint_as_float(v << 16); }
__device__ __forceinline__ float bf_hi(uint32_t v) { return __uint_as_float(v & 0xFFFF0000u); }
__device__ __forceinline__ float ex2(float x) { float y; asm("ex2.approx.ftz.f32 %0, %1;" : "=f"(y) : "f"(x)); return y; }
__device__ __forceinline__ void unpack8(uint4 v, float* f) {
  f[0] = bf_lo(v.x); f[1] = bf_hi(v.x); f[2] = bf_lo(v.y); f[3] = bf_hi(v.y);
  f[4] = bf_lo(v.z); f[5] = bf_hi(v.z); f[6] = bf_lo(v.w); f[7] = bf_hi(v.w);
}
__device__ __forceinline__ uint4 pack8(const float* f) { return make_uint4(pack2(f[0], f[1]), pack2(f[2], f[3]), pack2(f[4], f[5]), pack2(f[6], f[7])); }

template <typename F> __device__ __forceinline__ void normalize_row(uint4& a, uint4& b, float gain, F between) {
  float f[16], s[4], q[4];
  unpack8(a, f); unpack8(b, f + 8);
#pragma unroll
  for (int i = 0; i < 4; i++) {
    s[i] = (f[i] + f[4 + i]) + (f[8 + i] + f[12 + i]);
    q[i] = fmaf(f[i], f[i], fmaf(f[4 + i], f[4 + i], fmaf(f[8 + i], f[8 + i], f[12 + i] * f[12 + i])));
  }
  float sum = (s[0] + s[1]) + (s[2] + s[3]), sq = (q[0] + q[1]) + (q[2] + q[3]);
  between();
#pragma unroll
  for (int o = 16; o; o >>= 1) { sum += __shfl_xor_sync(0xffffffffu, sum, o); sq += __shfl_xor_sync(0xffffffffu, sq, o); }
  const float mean = sum * (1.f / DM);
  const float rstd = gain * rsqrtf(fmaxf(fmaf(-mean, mean, sq * (1.f / DM)), 0.f) + 1e-5f), shift = -mean * rstd;
#pragma unroll
  for (int i = 0; i < 16; i++) f[i] = fmaf(f[i], rstd, shift);
  a = pack8(f); b = pack8(f + 8);
}
__device__ __forceinline__ uint32_t add2(uint32_t a, uint32_t b) { uint32_t r; asm("add.rn.bf16x2 %0, %1, %2;" : "=r"(r) : "r"(a), "r"(b)); return r; }
__device__ __forceinline__ uint4 add8(uint4 a, uint4 b) { return make_uint4(add2(a.x, b.x), add2(a.y, b.y), add2(a.z, b.z), add2(a.w, b.w)); }

__device__ __forceinline__ uint32_t exp2_pair(float t0, float t1, uint32_t nhalf, uint32_t cman) {
  const uint32_t y = __byte_perm(__float_as_uint(t0), __float_as_uint(t1), 0x6521);
  uint32_t u, e, r;
  asm("lop3.b32 %0, %1, 0x007F007F, %2, 0xEA;" : "=r"(u) : "r"(y), "r"(nhalf));
  asm("lop3.b32 %0, %1, 0x7F807F80, %2, 0xEA;" : "=r"(e) : "r"(y), "r"(cman));
  asm("fma.rn.bf16x2 %0, %1, %2, %3;" : "=r"(r) : "r"(y), "r"(u), "r"(e));
  return r;
}
template <int HALF> __device__ __forceinline__ void exp_tile(const float (&s)[64], uint32_t (&p)[16], uint32_t nhalf, uint32_t cman) {
#pragma unroll
  for (int j = 0; j < 16; j++) {
    const float a = s[32 * HALF + 2 * j], b = s[32 * HALF + 2 * j + 1];
    p[j] = (POLY_MASK >> (8 * HALF + (j >> 1))) & 1 ? exp2_pair(a, b, nhalf, cman) : pack2(ex2(a), ex2(b));
  }
}
__device__ __forceinline__ void qk128(float (&s)[64], const uint32_t (&q)[8], uint64_t kd) {
  wgmma_rs_n128_t0(s, q[0], q[1], q[2], q[3], kd, 0);
  wgmma_rs_n128_t0(s, q[4], q[5], q[6], q[7], kd + 2, 1);
}
__device__ __forceinline__ void pv64(float (&o)[16], const uint32_t (&p)[16], uint64_t vd) {
#pragma unroll
  for (int j = 0; j < 4; j++) wgmma_rs_n32_t1(o, p[4 * j], p[4 * j + 1], p[4 * j + 2], p[4 * j + 3], vd + j * 128, 1);
}
template <int N> __device__ __forceinline__ void zero(float (&a)[N]) {
#pragma unroll
  for (int i = 0; i < N; i++) a[i] = 0.f;
  pin(a);
}
__device__ __forceinline__ float rcp(float x) { float y; asm("rcp.approx.ftz.f32 %0, %1;" : "=f"(y) : "f"(x)); return y; }
__device__ __forceinline__ float sqrt_fast(float x) { float y; asm("sqrt.approx.ftz.f32 %0, %1;" : "=f"(y) : "f"(x)); return y; }
__device__ __forceinline__ float gelu_half(float h) {
  const float u = h * fmaf(h * h, 0.28541926f, 1.59576912f);
  float t;
  asm("tanh.approx.f32 %0, %1;" : "=f"(t) : "f"(u));
  return fmaf(h, t, h);
}

template <int NB> __device__ __forceinline__ void bias_init(float (&acc)[4 * NB], uint32_t bias) {
#pragma unroll
  for (int j = 0; j < NB; j++)
    asm volatile("ld.shared.v4.f32 {%0, %1, %2, %3}, [%4];"
                 : "=f"(acc[4 * j]), "=f"(acc[4 * j + 1]), "=f"(acc[4 * j + 2]), "=f"(acc[4 * j + 3]) : "r"(bias + 64 * j) : "memory");
}
template <int N> __device__ __forceinline__ void gelu_tile(const float (&acc)[N], uint32_t* ga) {
#pragma unroll
  for (int j = 0; j < N / 2; j++) ga[j] = pack2(gelu_half(acc[2 * j]), gelu_half(acc[2 * j + 1]));
}

template <int V> struct Int { static constexpr int value = V; };

struct Params {
  const __nv_bfloat16 *x, *wk, *wv, *b1;
  Sync* sync;
  uint8_t* kv;
  uint8_t* hn;
  const __nv_bfloat16 *w1, *w2, *b2;
  __nv_bfloat16* out;
};

__global__ void __launch_bounds__(NTHREADS, 1)
fused_block_kernel(const Params P, const __grid_constant__ CUtensorMap tmWq, const __grid_constant__ CUtensorMap tmWqh,
                   const __grid_constant__ CUtensorMap tmWo, const __grid_constant__ CUtensorMap tmW1,
                   const __grid_constant__ CUtensorMap tmW2, const __grid_constant__ CUtensorMap tmOut) {
  extern __shared__ __align__(1024) uint8_t smem_raw[];
  const uint32_t sm = uni((uint32_t)__cvta_generic_to_shared(smem_raw));
  const uint32_t bars = sm + OFF_BAR;
  const int tid = threadIdx.x, lane = tid & 31, warp = __shfl_sync(0xffffffffu, tid >> 5, 0);
  const int pair = blockIdx.x >> 1, rank = blockIdx.x & 1;
  const int group = pair >> 2, fbase = (pair & 3) * 448;
  const int tok0 = pair * 32;
  const int wg = warp >> 2, wi = warp & 3, wtid = tid & 127;
  const int g = lane >> 2, c = lane & 3;
#define BAR(i) (bars + 8u * (i))
  auto load_slot = [&](const CUtensorMap* tm, uint32_t slot, int c0, int c1, uint32_t bar) {
    elect_expect(BAR(bar), SLOT);
    tma2d(sm + slot * SLOT, tm, c0, c1, BAR(bar));
  };
  uint32_t epoch = 0, gtarget = 0;
  float o[16];
  {
    const uint32_t xn = sm + 6 * SLOT, wkv = sm + 7 * SLOT;
    const bool act = lane < 28;
    if (wi == 0) {
      if (lane == 0) { mbar_init(BAR(B_X + wg), 1); fence_async_smem(); }
      __syncwarp();
      bulk_g2s(sm + wg * 7168, P.x + (size_t)(tok0 + 8 * wg) * DM, 7168, BAR(B_X + wg));
    }
    uint4 wr[4];
    const uint4* wsrc = reinterpret_cast<const uint4*>(rank ? P.wv : P.wk) + (tid >> 3) * 7 + (tid & 7);
#pragma unroll
    for (int it = 0; it < 4; it++) wr[it] = ldg128(wsrc + it * 448, (tid & 7) < 7 && (it < 3 || tid < 256));
    uint32_t b1v = 0;
    if (tid < 112) asm volatile("ld.global.nc.b32 %0, [%1];" : "=r"(b1v) : "l"(reinterpret_cast<const uint32_t*>(P.b1 + fbase + (rank ? (tid < 96 ? 256 : 32) : 0)) + tid));
    if (warp == 12) asm volatile("ld.relaxed.gpu.global.u32 %0, [%1];" : "=r"(epoch) : "l"(&P.sync->kv_count) : "memory");
    if (wi == 0 && wg >= 2) asm volatile("ld.relaxed.gpu.global.u32 %0, [%1];" : "=r"(gtarget) : "l"(&P.sync->grp[group].hn_count) : "memory");
    if (lane == 0) {
      if (warp == 1) {
#pragma unroll
        for (uint32_t i = B_WQ; i < B_KVD; i++) mbar_init(BAR(i), 1);
        fence_async_smem();
      } else if (warp == 6) {
#pragma unroll
        for (uint32_t i = B_KVD; i < B_HN; i++)
          mbar_init(BAR(i), i >= B_R1 ? 16 : i == B_KVD || i == B_QST ? 12 : i == B_QST2 ? 4 : 1);
        asm volatile("fence.mbarrier_init.release.cluster;" ::: "memory");
        mbar_expect(BAR(B_RCV1), HSLOT);
      } else if (warp == 7) {
#pragma unroll
        for (uint32_t i = B_HN; i < B_WE; i++) mbar_init(BAR(i), 1);
      } else if (warp == 8) {
#pragma unroll
        for (uint32_t i = B_WE; i < B_KVE; i++) mbar_init(BAR(i), i < B_RCV2 ? 8 : i < B_W2F ? 9 : 1);
        asm volatile("fence.mbarrier_init.release.cluster;" ::: "memory");
#pragma unroll
        for (uint32_t i = B_RCV2; i < B_W2F; i++) mbar_expect(BAR(i), 8192);
      } else if (warp >= 10 && warp < 14) {
        asm volatile("prefetch.tensormap [%0];" ::"l"(warp == 10 ? &tmWo : warp == 11 ? &tmW1 : warp == 12 ? &tmW2 : &tmOut) : "memory");
      } else if (warp == 9) {
        mbar_init(BAR(B_KVE), 16);
      }
    }
    __syncwarp();
    if (warp == 1) {
      elect_expect(BAR(B_WQ + 6), SLOT);
      tma2d(sm + 5 * SLOT, &tmWqh, 192 + 32 * rank, 0, BAR(B_WQ + 6));
      tma2d(sm + 5 * SLOT + HSLOT, &tmWqh, 192 + 32 * rank, 224, BAR(B_WQ + 6));
#pragma unroll
      for (int i = 0; i < 3; i++) load_slot(&tmWq, 2 + i, 256 * rank + 64 * i, 0, B_WQ + i);
      load_slot(&tmWq, 1, 256 * rank + 64, 224, B_WQ + 4);
    }
    asm volatile("barrier.cluster.arrive.relaxed.aligned;" ::: "memory");
    bar_sync(1, NTHREADS);
    uint32_t wa[2], xa[2];
#pragma unroll
    for (int h = 0; h < 2; h++) {
      const uint32_t u = 2 * (tid & 7) + h, odd = u == 14 ? 0 : u >= 7, j = u >= 14 ? 7 : u - 7 * odd;
      wa[h] = wkv + (tid >> 3) * 128 + odd * 64 + (((j >> 1) ^ ((tid >> 3) & 3)) << 4) + (j & 1) * 8;
    }
    xa[0] = xn + (lane >> 3) * 4096 + warp * 256 + (((lane & 7) ^ (2 * warp & 7)) << 4);
    xa[1] = xn + ((lane + 28) >> 3) * 4096 + warp * 256 + ((((lane + 28) & 7) ^ (2 * warp & 7)) << 4);
    mbar_wait(BAR(B_X + wg));
    uint4 xr[2][2];
#pragma unroll
    for (int i = 0; i < 4; i++) xr[i >> 1][i & 1] = act ? lds128(sm + warp * 1792 + i * 448 + lane * 16) : make_uint4(0, 0, 0, 0);
#pragma unroll
    for (int r = 0; r < 2; r++) {
      normalize_row(xr[r][0], xr[r][1], 1.f, [&]() {
#pragma unroll
        for (int it = 2 * r; it < 2 * r + 2; it++)
          if (it < 3 || tid < 256) { sts64(wa[0] + it * 8192, wr[it].x, wr[it].y); sts64(wa[1] + it * 8192, wr[it].z, wr[it].w); }
      });
      if (act) { sts128((xa[0] + r * 128) ^ (r * 16), xr[r][0]); sts128((xa[1] + r * 128) ^ (r * 16), xr[r][1]); }
    }
    if (tid < 112) {
      const uint32_t lo = __float_as_uint(0.5f * bf_lo(b1v)), hi = __float_as_uint(0.5f * bf_hi(b1v));
      sts128(sm + OFF_B1 + tid * 16, make_uint4(lo, hi, lo, hi));
    }
    epoch = (epoch >> 7) + 1;
    gtarget = (gtarget & ~7u) + 8;
    fence_async_smem();
    bar_sync(1, NTHREADS);
    const uint32_t xd = dlo(xn, 16);
    const uint32_t qst = wkv + 4096;
    const float qs = 0.18898224f * 1.44269504f;
    const int mi = lane >> 3;
    zero(o);
    if (wg == 3) {
      uint32_t al = dlo(sm + 5 * SLOT, 2 * SLOT), bl = xd;
      mbar_wait(BAR(B_WQ + 6));
#pragma unroll 1
      for (int kb = 0; kb < 7; kb++, al += 256, bl += 256) {
        const uint64_t ad = desc<HI64>(al), bd = desc<HI128>(bl);
        wg_fence();
#pragma unroll
        for (int ks = 0; ks < 4; ks++) wgmma_ss_n32_t10(o, ad + ks * 64, bd + ks * 2, 1);
        wg_commit();
      }
      wg_wait<0>(); pin(o);
      bar_sync(5, 128);
#pragma unroll
      for (int i = 0; i < 2; i++) {
        const int tok = 16 * i + (mi >> 1) * 8 + (lane & 7), ch = 2 * (wi & 1) + (mi & 1);
        const float sc = wi < 2 ? qs : 1.f;
        const uint32_t a = wi < 2 ? qst + tok * 512 + (rank ? 0 : 384) + ((ch ^ (tok & 7)) << 4) : wkv + tok * 64 + ((ch ^ ((tok >> 1) & 3)) << 4);
        stsm4t(a, pack2(o[8 * i] * sc, o[8 * i + 1] * sc), pack2(o[8 * i + 2] * sc, o[8 * i + 3] * sc),
               pack2(o[8 * i + 4] * sc, o[8 * i + 5] * sc), pack2(o[8 * i + 6] * sc, o[8 * i + 7] * sc));
      }
      warp_arrive(BAR(B_QST), lane);
      bar_sync(5, 128);
      const int tok = wtid >> 2, key = tok0 + tok;
      uint4 v = lds128(wkv + tok * 64 + ((c ^ ((tok >> 1) & 3)) << 4));
      bar_arrive(6, NTHREADS);
      float f[8];
      unpack8(v, f);
      if (c == 3) {
        const uint32_t flag = (rank == 0 && ((POLY_MASK >> ((key >> 3) & 15)) & 1)) ? 0x3F80u : 0u;
        v.z = 0x3F80u | (flag << 16);
        v.w = flag * 0x10001u;
      }
      *reinterpret_cast<uint4*>(P.kv + key * 128 + (((rank * 4 + c) ^ (key & 7)) << 4)) = v;
      if (rank == 0) {
        float n = (fmaf(f[0], f[0], f[1] * f[1]) + fmaf(f[2], f[2], f[3] * f[3])) + (fmaf(f[4], f[4], f[5] * f[5]) + fmaf(f[6], f[6], f[7] * f[7]));
        n += __shfl_xor_sync(0xffffffffu, n, 1);
        n += __shfl_xor_sync(0xffffffffu, n, 2);
        const uint32_t m = __reduce_max_sync(0xffffffffu, __float_as_uint(n));
        if (lane == 0) sts32(sm + OFF_KMAX + 16 + 4 * wi, m);
      }
      bar_sync(5, 128);
      if (wi == 0) {
        if (rank == 0 && lane == 0) {
          const uint4 m = lds128(sm + OFF_KMAX + 16);
          asm volatile("red.relaxed.gpu.global.max.u64 [%0], %1;" ::"l"(&P.sync->kmax), "l"(((unsigned long long)epoch << 32) | max(max(m.x, m.y), max(m.z, m.w))) : "memory");
        }
        __syncwarp();
        fence_async();
        elect_red(&P.sync->kv_count);
      }
    } else {
      if (warp == 0) load_slot(&tmWq, 0, 256 * rank, 224, B_WQ + 3);
      bar_sync(6, NTHREADS);
#pragma unroll 1
      for (int h = 0; h < 2; h++) {
        const uint32_t hu = uni(h);
        const uint64_t ad = desc<HI128>(dlo(sm + ((0x510432 >> (4 * (3 * hu + wg))) & 7) * SLOT, 16));
        const uint64_t be = desc<HI128>(xd + hu * (3 * 256 + 4)), bo = desc<HI128>(xd + hu * (4 * 256 - 4));
        mbar_wait(BAR(B_WQ + 3 * h + wg));
        wg_fence();
#pragma unroll
        for (int ks = 0; ks < 14; ks++) wgmma_ss_n32_t10(o, ad + ks * 128, ((ks & 2) ? bo : be) + (ks >> 2) * 256 + (ks & 3) * 2, 1);
        wg_commit(); wg_wait<0>(); pin(o);
        if (h == 0) {
          lane0_arrive(BAR(B_KVD), lane);
          if (warp == 8) load_slot(&tmWq, 5, 256 * rank + 128, 224, B_WQ + 5);
        }
      }
#pragma unroll
      for (int i = 0; i < 2; i++) {
        const int tok = 16 * i + (mi >> 1) * 8 + (lane & 7), ch = 4 * rank + 8 * wg + 2 * wi + (mi & 1);
        stsm4t(qst + tok * 512 + (ch >> 3) * 128 + (((ch & 7) ^ (tok & 7)) << 4), pack2(o[8 * i] * qs, o[8 * i + 1] * qs), pack2(o[8 * i + 2] * qs, o[8 * i + 3] * qs),
               pack2(o[8 * i + 4] * qs, o[8 * i + 5] * qs), pack2(o[8 * i + 6] * qs, o[8 * i + 7] * qs));
      }
      warp_arrive(BAR(wg == 2 ? B_QST2 : B_QST), lane);
    }
  }
  uint32_t q[8];
  bool fast;
  {
    const uint32_t qst = sm + 7 * SLOT + 4096;
    const int tk = (wi & 1) * 16 + g, col = 56 * wg + 28 * (wi >> 1) + 2 * c;
    uint32_t qa[4];
#pragma unroll
    for (int i = 0; i < 4; i++) {
      const int off = (col + 8 * i) * 2;
      qa[i] = qst + tk * 512 + (off & ~0x70) + ((off ^ (g << 4)) & 0x70);
    }
    pin(qa);
    auto poll_kv = [&]() {
      unsigned long long lo, hi;
      asm volatile("{.reg .b128 v; ld.acquire.gpu.global.b128 v, [%2]; mov.b128 {%0, %1}, v;}" : "=l"(lo), "=l"(hi) : "l"(P.sync) : "memory");
      if ((int32_t)uni((uint32_t)lo - epoch * 128u) < 0) return true;
      mbar_wait(BAR(B_KVD));
      sts32(sm + OFF_KMAX, (uint32_t)hi);
      elect_arrive(BAR(B_KMAX));
      bulk_g2s(sm + OFF_RING, P.kv, 16384, BAR(B_KVF));
      return false;
    };
    bool pending = warp == 12;
    while (pending && !uni(mbar_try(BAR(B_QST2)))) pending = poll_kv();
    float n0 = 0.f, n1 = 0.f;
    mbar_wait(BAR(B_QST));
    if (wg >= 2) mbar_wait(BAR(B_QST2));
#pragma unroll
    for (int i = 0; i < 8; i++) {
      q[i] = i < 6 || c < 2 ? lds32(qa[i >> 1] + (i & 1) * 4096) : 0u;
      const float lo = bf_lo(q[i]), hi = bf_hi(q[i]);
      if (i & 1) n1 = fmaf(lo, lo, fmaf(hi, hi, n1)); else n0 = fmaf(lo, lo, fmaf(hi, hi, n0));
    }
    fence_async_smem();
    n0 += __shfl_xor_sync(0xffffffffu, n0, 1); n0 += __shfl_xor_sync(0xffffffffu, n0, 2);
    n1 += __shfl_xor_sync(0xffffffffu, n1, 1); n1 += __shfl_xor_sync(0xffffffffu, n1, 2);
    asm volatile("barrier.cluster.wait.acquire.aligned;" ::: "memory");
    for (uint32_t i = 0; pending; i++) {
      pending = poll_kv();
      if (i > SPIN_LIMIT) __trap();
    }
    mbar_wait(BAR(B_KMAX));
    const float k2 = __uint_as_float(lds32(sm + OFF_KMAX)) * 1.03125f;
    const float m0 = sqrt_fast(n0 * k2), m1 = sqrt_fast(n1 * k2);
    fast = __shfl_sync(0xffffffffu, (int)bar_all(2 + wg, 128, m0 <= SHIFT_LIMIT && m1 <= SHIFT_LIMIT), 0);
    if (fast) {
      if (c == 2) { q[6] = pack2(-m0, 256.f); q[7] = pack2(-m1, 256.f); }
      if (c == 3) { q[6] = pack2(126.5f, -0.09894f); q[7] = q[6]; }
    }
  }
  {
    const uint32_t kd0 = dlo(sm + OFF_RING, 16);
    zero(o);
    auto mine = [&](int t) { return warp == 12 + (t & 3); };
    auto on_free = [&](int t) {
      if (t == 14) mbar_wait(BAR(B_KVE)); else bar_sync(8 + (t & 3), NTHREADS);
      if (t < 12) bulk_g2s(sm + OFF_RING + (t & 3) * 16384, P.kv + (t + 4) * 16384, 16384, BAR(B_KVF + (t & 3)));
      if ((0x5015 >> t) & 1) {
        if (t == 14) {
          elect_arrive_remote(mapa(BAR(B_PRDY), rank ^ 1));
        } else {
          const int u = t == 12 ? 5 : t;
          load_slot(&tmWo, (0x276510 >> (4 * u)) & 7, 64 * u, 224 * rank, B_WO + u);
          if (t < 4) {
            load_slot(&tmWo, t ? 6 : 1, 64 * u + 64, 224 * rank, B_WO + u + 1);
            prefetch_l2(reinterpret_cast<const uint8_t*>(t ? P.w2 : P.w1) + blockIdx.x * 12544, 12544);
          }
        }
      }
    };
    auto first_loads = [&]() {
      if (wi == 0 && wg < 3) bulk_g2s(sm + OFF_RING + (1 + wg) * 16384, P.kv + (1 + wg) * 16384, 16384, BAR(B_KVF + 1 + wg));
    };
    float sw[64];
    uint32_t pa[16], pb[16];
    zero(sw);
    if (fast) {
      const uint32_t nhalf = hold(0xBF00BF00u, lane), cman = hold(0x00030003u, lane);
      uint64_t kd = desc<HI128>(kd0);
      first_loads();
      mbar_wait(BAR(B_KVF), 0);
#pragma unroll 1
      for (int k = 0; k < 4; k++) {
#pragma unroll
        for (int sl = 0; sl < 4; sl++) {
          const int t = 4 * k + sl;
          asm volatile("" : "+l"(kd));
          wg_fence(); qk128(sw, q, kd + sl * 1024); wg_commit();
          bar_arrive_if(t > 0 && t < 14 && !mine(t - 1), 8 + ((sl + 3) & 3), NTHREADS);
          if (sl == 3) lane0_arrive(BAR(B_KVE), lane + (k < 3));
          if (t >= 2 && t < 15 && mine(t - 2)) on_free(t - 2);
          if (sl < 3 || k < 3) mbar_wait_hot(BAR(B_KVF + ((sl + 1) & 3)), (sl == 3 ? k + 1 : k) & 1);
          wg_wait<0>(); pin(sw);
          exp_tile<0>(sw, pa, nhalf, cman);
          exp_tile<1>(sw, pb, nhalf, cman);
          pin(pa); pin(pb);
          wg_fence(); pv64(o, pa, kd + sl * 1024 + 4); pv64(o, pb, kd + sl * 1024 + 512 + 4); wg_commit();
          wg_wait<0>(); pin(o); pin(pa); pin(pb);
        }
      }
      if (mine(14)) on_free(14);
    } else {
      float m0 = -INFINITY, m1 = -INFINITY;
      first_loads();
#pragma unroll 1
      for (int t = 0; t < 16; t++) {
        const uint64_t kd = desc<HI128>(kd0 + (t & 3) * 1024);
        mbar_wait(BAR(B_KVF + (t & 3)), (t >> 2) & 1);
        wg_fence(); qk128(sw, q, kd); wg_commit(); wg_wait<0>(); pin(sw);
        float t0 = m0, t1 = m1;
#pragma unroll
        for (int j = 0; j < 16; j++) { t0 = fmaxf(t0, fmaxf(sw[4 * j], sw[4 * j + 1])); t1 = fmaxf(t1, fmaxf(sw[4 * j + 2], sw[4 * j + 3])); }
        t0 = fmaxf(t0, __shfl_xor_sync(0xffffffffu, t0, 1)); t0 = fmaxf(t0, __shfl_xor_sync(0xffffffffu, t0, 2));
        t1 = fmaxf(t1, __shfl_xor_sync(0xffffffffu, t1, 1)); t1 = fmaxf(t1, __shfl_xor_sync(0xffffffffu, t1, 2));
        const float a0 = ex2(m0 - t0), a1 = ex2(m1 - t1);
        m0 = t0; m1 = t1;
#pragma unroll
        for (int j = 0; j < 4; j++) { o[4 * j] *= a0; o[4 * j + 1] *= a0; o[4 * j + 2] *= a1; o[4 * j + 3] *= a1; }
#pragma unroll
        for (int j = 0; j < 16; j++) {
          const float m = (j & 1) ? m1 : m0;
          pa[j] = pack2(ex2(sw[2 * j] - m), ex2(sw[2 * j + 1] - m));
          pb[j] = pack2(ex2(sw[32 + 2 * j] - m), ex2(sw[33 + 2 * j] - m));
        }
        pin(o); pin(pa); pin(pb);
        wg_fence(); pv64(o, pa, kd + 4); pv64(o, pb, kd + 512 + 4); wg_commit();
        wg_wait<0>(); pin(o); pin(pa); pin(pb);
        bar_arrive_if(t < 13 && !mine(t), 8 + (t & 3), NTHREADS);
        if (t == 14) lane0_arrive(BAR(B_KVE), lane);
        if (mine(t) && t != 13 && t != 15) on_free(t);
      }
    }
  }
  auto load_w1 = [&](int kb, int half, uint32_t pos) {
    elect_expect(BAR(B_WF + pos), 16384);
    const int c0 = fbase + 256 * rank + 128 * half;
    tma2d(sm + pos * 16384, &tmW1, c0, 64 * kb, BAR(B_WF + pos));
    tma2d(sm + pos * 16384 + 8192, &tmW1, half && rank ? fbase + 224 : c0 + 64, 64 * kb, BAR(B_WF + pos));
  };
  uint4 init0, init1;
  {
    const int mytok = tok0 + 16 * rank + warp;
    const bool act = lane < 28;
    const uint32_t ost = sm + 3 * SLOT, rcv = ost + HSLOT, hbuf = sm + 5 * SLOT;
    const float i0 = rcp(__shfl_sync(0xffffffffu, o[12], (lane & ~3) | 2)), i1 = rcp(__shfl_sync(0xffffffffu, o[14], (lane & ~3) | 2));
    float o2[16];
    zero(o2);
    mbar_wait(BAR(B_KVE));
    {
      const int k0 = (2 * wg + (wi >> 1)) * 28 + 2 * c;
      const uint32_t a = ost + (k0 >> 3) * 512 + (k0 & 7) * 2 + ((((wi ^ rank) & 1) * 16 + g) << 4);
#pragma unroll
      for (int j = 0; j < 4; j++) {
        if (j < 3 || c < 2) {
          sts32(a + 512 * j, pack2(o[4 * j] * i0, o[4 * j + 1] * i0));
          sts32(a + 512 * j + 128, pack2(o[4 * j + 2] * i1, o[4 * j + 3] * i1));
        }
      }
    }
    fence_async_smem();
    bar_sync(1, NTHREADS);
    if (warp == 12) load_slot(&tmWo, 4, 64 * 6, 224 * rank, B_WO + 6);
    const uint32_t peer_rcv = mapa(rcv, rank ^ 1) + wtid * 16 + wg * 2048, peer_bar = mapa(BAR(B_RCV1), rank ^ 1);
    auto project = [&](float (&a)[16], uint32_t slot, uint32_t bar) {
      uint64_t ad = desc<HI128>(dlo(sm + slot * SLOT, 16)), bd = desc<HI0>(dlo(ost, 512));
      asm volatile("" : "+l"(ad), "+l"(bd));
      mbar_wait(BAR(bar));
      wg_fence();
#pragma unroll
      for (int ks = 0; ks < 14; ks++) wgmma_ss_n32_t10(a, ad + ks * 128, bd + ks * 64, ks > 0);
    };
    project(o, wg < 2 ? wg : wg + 3, B_WO + wg);
    wg_commit();
    if (wg < 3) project(o2, wg == 0 ? 7 : 2 * wg, B_WO + 4 + wg);
    wg_commit();
    uint4 xr[2], br[2];
    {
      const uint4* row = reinterpret_cast<const uint4*>(P.x + (size_t)mytok * DM);
      const uint4* b2 = reinterpret_cast<const uint4*>(P.b2);
      xr[0] = ldg128(row + lane, act);
      xr[1] = ldg128(row + lane + 28, act);
      br[0] = ldg128(b2 + lane, act);
      br[1] = ldg128(b2 + lane + 28, act);
    }
    mbar_wait(BAR(B_PRDY));
    wg_wait<1>(); pin(o);
    { const uint4 v = pack8(o + 8); st_async4(peer_rcv, v.x, v.y, v.z, v.w, peer_bar); }
    wg_wait<0>(); pin(o2);
    elect_arrive(BAR(B_R1));
    if (wg < 3) { const uint4 v = pack8(o2 + 8); st_async4(peer_rcv + 8192, v.x, v.y, v.z, v.w, peer_bar); }
    const uint32_t ta = hold(hbuf + ((lane >> 4) * 8 + (lane & 7)) * 896 + wg * 128 + (((2 * wi + ((lane >> 3) & 1)) ^ (lane & 7)) << 4), lane);
    const uint32_t ra0 = hold(hbuf + warp * 896 + (lane >> 3) * 128 + (((lane ^ warp) & 7) << 4), lane);
    const uint32_t ra1 = hold(hbuf + warp * 896 + ((lane + 28) >> 3) * 128 + ((((lane + 28) ^ warp) & 7) << 4), lane);
    const uint32_t hrow = group * (7 * 16384) + (mytok & 127) * 128;
    const uint32_t ho0 = hold(hrow + (lane >> 3) * 16384 + (((lane ^ mytok) & 7) << 4), lane);
    const uint32_t ho1 = hold(hrow + ((lane + 28) >> 3) * 16384 + ((((lane + 28) ^ mytok) & 7) << 4), lane);
    mbar_wait(BAR(B_R1));
    if (warp == 12) {
#pragma unroll 1
      for (int kb = 0; kb < 3; kb++) load_w1(kb, 0, 2 - kb);
    }
    mbar_wait(BAR(B_RCV1));
#pragma unroll
    for (int rd = 0; rd < 2; rd++) {
      if (rd == 0 || wg < 3) {
        const uint4 v = add8(pack8(rd ? o2 : o), lds128(rcv + (wg + 4 * rd) * 2048 + wtid * 16));
        stsm4t(ta + rd * 512, v.x, v.y, v.z, v.w);
      }
    }
    fence_async_smem();
    bar_sync(1, NTHREADS);
    if (act) {
      xr[0] = add8(xr[0], lds128(ra0));
      xr[1] = add8(xr[1], lds128(ra1));
    }
    if (wi == 0) load_w1(3 + wg, 0, 6 - wg);
    init0 = add8(xr[0], br[0]);
    init1 = add8(xr[1], br[1]);
    normalize_row(xr[0], xr[1], 0.5f, []() {});
    if (act) {
      *reinterpret_cast<uint4*>(P.hn + ho0) = xr[0];
      *reinterpret_cast<uint4*>(P.hn + ho1) = xr[1];
    }
    bar_arrive_if(warp != 8, 7, NTHREADS);
  }
  auto store_init = [&]() {
    uint4* orow = reinterpret_cast<uint4*>(P.out + (size_t)(tok0 + 16 * rank + warp) * DM) + lane;
    if (lane < 28) { orow[0] = init0; orow[28] = init1; }
    __syncwarp();
    elect_arrive(BAR(B_OUTW));
  };
  if (wg >= 2) {
    if (warp != 8) { mbar_wait(BAR(B_HN + 4)); store_init(); }
    if (warp == 8) {
      bar_sync(7, NTHREADS);
      fence_async();
      elect_red(&P.sync->grp[group].hn_count);
      wait_count(&P.sync->grp[group].hn_count, gtarget);
#pragma unroll 1
      for (int kb = 0; kb < 7; kb++) {
        if (kb >= 3) mbar_wait(BAR(B_HN + kb - 3));
        bulk_g2s(sm + 4 * SLOT + kb * 16384, P.hn + (group * 7 + kb) * 16384, 16384, BAR(B_HN + kb));
      }
      uint32_t pos = 2;
#pragma unroll 1
      for (int i = 0; i < 7; i++) {
        if (i == 3) store_init();
        mbar_wait(BAR(B_WE + pos), 0);
        load_w1(i, 1, pos);
        pos = pos ? pos - 1 : 6;
      }
#pragma unroll 1
      for (int p = 0; p < 7; p++) {
        if (p < 3) mbar_wait(BAR(B_WE + (p == 0 ? 0 : p == 1 ? 5 : 3)), 1);
        if (p >= 4) mbar_wait(BAR(B_W2E + p - 4));
        load_slot(&tmW2, (0x2130 >> (4 * (p & 3))) & 3, 64 * p, fbase + 224 * rank, B_W2F + p);
      }
    }
    if (warp == 12) {
      mbar_wait(BAR(B_OUTW));
      fence_async();
      elect_red(&P.sync->grp[group].out_count);
      wait_count(&P.sync->grp[group].out_count, gtarget);
    }
    if (wg == 3) {
      const uint32_t rcv = sm + 4 * SLOT + wtid * 16, stg = sm + 6 * SLOT;
      const uint32_t st0 = stg + wi * 1024 + (lane & 7) * 128 + (((lane >> 3) ^ (lane & 7)) << 4);
      const int ogrp = uni(8 * group), orow = uni(8 * rank);
      __syncwarp();
#pragma unroll
      for (int p = 0; p < 7; p++) {
        uint4 v[4];
        mbar_wait_hot(BAR(B_RCV2 + p));
#pragma unroll
        for (int i = 0; i < 4; i++) v[i] = add8(lds128(rcv + p * 8192 + i * 2048), lds128(rcv + 2 * SLOT + p * 8192 + i * 2048));
        bar_sync(5, 128);
#pragma unroll
        for (int i = 0; i < 4; i++) stsm4((st0 ^ (64 * (i & 1))) + (i >> 1) * 4096 + p * 8192, v[i].x, v[i].y, v[i].z, v[i].w);
        fence_async_smem();
        bar_sync(5, 128);
        if (wi == 0)
          asm volatile("{.reg .pred p; elect.sync _|p, 0xffffffff;\n"
                       "@p cp.reduce.async.bulk.tensor.3d.global.shared::cta.add.tile.bulk_group [%0, {%2, %3, %4}], [%1];\n"
                       "@p cp.async.bulk.commit_group;}" ::"l"(&tmOut), "r"(stg + p * 8192), "r"(64 * p), "r"(orow), "r"(ogrp) : "memory");
      }
      if (wi == 0) asm volatile("cp.async.bulk.wait_group.read 0;" ::: "memory");
    }
    return;
  }
  uint32_t ga[56];
  {
    const uint32_t ad0 = dlo(sm + 4 * SLOT + wg * 8192, 16), bd0 = dlo(sm, 8192);
    {
      float acc[64];
      bias_init<16>(acc, sm + OFF_B1 + 16 * c);
      uint32_t pos = 2, prev = 0;
#pragma unroll 1
      for (int kb = 0; kb < 7; kb++) {
        const uint64_t ad = desc<HI128>(ad0 + kb * 1024), bd = desc<HI128>(bd0 + pos * 1024);
        if (wg == rank && kb == 4) bar_sync(6, 256);
        mbar_wait(BAR(B_WF + pos), 0);
        mbar_wait(BAR(B_HN + kb));
        wg_fence();
#pragma unroll
        for (int ks = 0; ks < 4; ks++) wgmma_ss_n128_t01(acc, ad + ks * 2, bd + ks * 128, 1);
        wg_commit();
        if (wg != rank && kb == 6) bar_arrive(6, 256);
        if (kb == 4) store_init();
        wg_wait<1>();
        lane0_arrive(BAR(B_WE + prev), lane + (kb == 0));
        prev = pos;
        pos = pos ? pos - 1 : 6;
      }
      wg_wait<0>(); pin(acc);
      lane0_arrive(BAR(B_WE + 3), lane);
      gelu_tile(acc, ga);
#pragma unroll
      for (int i = 0; i < 32; i++) asm volatile("" : "+r"(ga[i])::"memory");
    }
    {
      float acc[48];
      bias_init<12>(acc, sm + OFF_B1 + 1024 + 16 * c);
      uint32_t pos = 2, prev = 0;
#pragma unroll 1
      for (int kb = 0; kb < 7; kb++) {
        const uint64_t ad = desc<HI128>(ad0 + kb * 1024), bd = desc<HI128>(bd0 + pos * 1024);
        mbar_wait(BAR(B_WF + pos), 1);
        wg_fence();
#pragma unroll
        for (int ks = 0; ks < 4; ks++) wgmma_ss_n96_t01(acc, ad + ks * 2, bd + ks * 128, 1);
        wg_commit(); wg_wait<1>();
        lane0_arrive(BAR(B_WE + prev), lane + (kb == 0));
        prev = pos;
        pos = pos ? pos - 1 : 6;
      }
      wg_wait<0>(); pin(acc);
      elect_arrive(BAR(B_WE + 3)); elect_arrive(BAR(B_F1)); elect_arrive_remote(mapa(BAR(B_PF1), rank ^ 1));
      gelu_tile(acc, ga + 32);
    }
    pin(ga);
  }
  {
    const uint32_t bda = uni(dlo(sm, 16) + 256 * rank), bdb = uni(dlo(sm, 16) - 1536 * rank);
    uint32_t loc = sm + 6 * SLOT + wg * 4096 + wtid * 16, rem = mapa(loc - 2 * SLOT, rank ^ 1);
    uint32_t rbar = uni(mapa(BAR(B_RCV2), rank ^ 1)), slots = 0x1302130;
    float a[32];
    zero(a);
#pragma unroll 1
    for (int p = 0; p < 7; p++, slots >>= 4, loc += 8192, rem += 8192, rbar += 8) {
      const uint32_t off = (slots & 3) * (SLOT >> 4);
      const uint64_t da = desc<HI128>(bda + off), db = desc<HI128>(bdb + off);
      mbar_wait_hot(BAR(B_W2F + p));
      wg_fence();
#pragma unroll
      for (int ks = 0; ks < 14; ks++)
        wgmma_rs_n64_t1(a, ga[4 * ks], ga[4 * ks + 1], ga[4 * ks + 2], ga[4 * ks + 3], (ks < 12 ? da : db) + ks * 128, ks > 0);
      wg_commit(); wg_wait<0>(); pin(a);
      elect_arrive(BAR(B_W2E + p));
      if (p == 0) { mbar_wait(BAR(B_F1)); mbar_wait(BAR(B_PF1)); }
      auto ship = [&](auto own) {
#pragma unroll
        for (int i = 0; i < 2; i++) {
          const float* r = a + 16 * i + 2 * (1 - own.value);
          st_async4(rem + i * 2048, pack2(r[0], r[1]), pack2(r[4], r[5]), pack2(r[8], r[9]), pack2(r[12], r[13]), rbar);
        }
#pragma unroll
        for (int i = 0; i < 2; i++) {
          const float* r = a + 16 * i + 2 * own.value;
          sts128(loc + i * 2048, make_uint4(pack2(r[0], r[1]), pack2(r[4], r[5]), pack2(r[8], r[9]), pack2(r[12], r[13])));
        }
      };
      if (rank) ship(Int<1>()); else ship(Int<0>());
      __syncwarp();
      elect_arrive(BAR(B_RCV2 + p));
    }
  }
#undef BAR
}

typedef CUresult (*EncodeFn)(CUtensorMap*, CUtensorMapDataType, cuuint32_t, void*, const cuuint64_t*, const cuuint64_t*,
                             const cuuint32_t*, const cuuint32_t*, CUtensorMapInterleave, CUtensorMapSwizzle,
                             CUtensorMapL2promotion, CUtensorMapFloatOOBfill);

void encode(EncodeFn fn, CUtensorMap* tm, const void* base, int rank, const cuuint64_t* dims, const cuuint64_t* strides,
            const cuuint32_t* box, CUtensorMapSwizzle sw) {
  const cuuint32_t es[3] = {1, 1, 1};
  fn(tm, CU_TENSOR_MAP_DATA_TYPE_BFLOAT16, rank, const_cast<void*>(base), dims, strides, box, es, CU_TENSOR_MAP_INTERLEAVE_NONE,
     sw, CU_TENSOR_MAP_L2_PROMOTION_L2_128B, CU_TENSOR_MAP_FLOAT_OOB_FILL_NONE);
}

}

extern "C" void kernel_launch(void* const* d_in, const int* in_sizes, int n_in, void* d_out, int out_size) {
  (void)in_sizes; (void)n_in; (void)out_size;
  static EncodeFn fn = nullptr;
  if (!fn) {
    void* p = nullptr;
    cudaDriverEntryPointQueryResult st;
    cudaGetDriverEntryPoint("cuTensorMapEncodeTiled", &p, cudaEnableDefault, &st);
    fn = reinterpret_cast<EncodeFn>(p);
    cudaFuncSetAttribute(fused_block_kernel, cudaFuncAttributeMaxDynamicSharedMemorySize, SMEM_BYTES);
  }
  CUtensorMap tmWq, tmWqh, tmWo, tmW1, tmW2, tmOut;
  {
    const cuuint64_t dims[2] = {DM, DM}, str[1] = {DM * 2};
    const cuuint32_t box[2] = {64, 224};
    encode(fn, &tmWq, d_in[1], 2, dims, str, box, CU_TENSOR_MAP_SWIZZLE_128B);
    encode(fn, &tmWo, d_in[4], 2, dims, str, box, CU_TENSOR_MAP_SWIZZLE_128B);
    const cuuint32_t boxh[2] = {32, 224};
    encode(fn, &tmWqh, d_in[1], 2, dims, str, boxh, CU_TENSOR_MAP_SWIZZLE_64B);
  }
  {
    const cuuint64_t dims[2] = {FF, DM}, str[1] = {FF * 2};
    const cuuint32_t box[2] = {64, 64};
    encode(fn, &tmW1, d_in[6], 2, dims, str, box, CU_TENSOR_MAP_SWIZZLE_128B);
  }
  {
    const cuuint64_t dims[2] = {DM, FF}, str[1] = {DM * 2};
    const cuuint32_t box[2] = {64, 224};
    encode(fn, &tmW2, d_in[8], 2, dims, str, box, CU_TENSOR_MAP_SWIZZLE_128B);
  }
  {
    const cuuint64_t dims[3] = {DM, 16, SEQ / 16}, str[2] = {DM * 2, 16 * DM * 2};
    const cuuint32_t box[3] = {64, 8, 8};
    encode(fn, &tmOut, d_out, 3, dims, str, box, CU_TENSOR_MAP_SWIZZLE_128B);
  }
  Params P;
  P.x = static_cast<const __nv_bfloat16*>(d_in[0]);
  P.wk = static_cast<const __nv_bfloat16*>(d_in[2]);
  P.wv = static_cast<const __nv_bfloat16*>(d_in[3]);
  P.w1 = static_cast<const __nv_bfloat16*>(d_in[6]);
  P.b1 = static_cast<const __nv_bfloat16*>(d_in[7]);
  P.w2 = static_cast<const __nv_bfloat16*>(d_in[8]);
  P.b2 = static_cast<const __nv_bfloat16*>(d_in[9]);
  P.out = static_cast<__nv_bfloat16*>(d_out);
  cudaGetSymbolAddress(reinterpret_cast<void**>(&P.sync), g_sync);
  cudaGetSymbolAddress(reinterpret_cast<void**>(&P.kv), g_kv);
  cudaGetSymbolAddress(reinterpret_cast<void**>(&P.hn), g_hn);

  cudaLaunchConfig_t cfg = {};
  cfg.gridDim = dim3(128);
  cfg.blockDim = dim3(NTHREADS);
  cfg.dynamicSmemBytes = SMEM_BYTES;
  cfg.stream = cudaStreamPerThread;
  cudaLaunchAttribute at[1];
  at[0].id = cudaLaunchAttributeClusterDimension;
  at[0].val.clusterDim.x = 2; at[0].val.clusterDim.y = 1; at[0].val.clusterDim.z = 1;
  cfg.attrs = at;
  cfg.numAttrs = 1;
  cudaLaunchKernelEx(&cfg, fused_block_kernel, P, tmWq, tmWqh, tmWo, tmW1, tmW2, tmOut);
}
```
